```python
import torch

def _softmax(x, axis=-1):
    return torch.softmax(x, dim=axis)
def _gelu(x):
    return torch.nn.functional.gelu(x, approximate="tanh")
def _silu(x):
    return torch.nn.functional.silu(x)
def _sigmoid(x):
    return torch.sigmoid(x)
def _layernorm(x, axis=-1, eps=1e-5):
    m = x.mean(dim=axis, keepdim=True)
    v = x.var(dim=axis, keepdim=True, unbiased=False)
    return (x - m) / torch.sqrt(v + eps)
def _scatter_add(tgt, idx, src, axis=0):
    return tgt.clone().index_add_(axis, idx, src)
def _segment_sum(src, seg, n):
    out = torch.zeros((n,) + src.shape[1:], dtype=src.dtype)
    return out.index_add_(0, seg, src)
def _pad(x, pw):
    flat = tuple(v for pair in reversed(pw) for v in pair)
    return torch.nn.functional.pad(x, flat)

kernel_name = 'gated_mix__spectral_fnet__glu_gated_glu__prompt'

def setup_inputs():

    _w = (lambda a: (lambda t: t.to(torch.bfloat16) if t.is_floating_point() else t)(torch.as_tensor(a)))
    def _A_setup():
        B, S, D = 1, 2048, 1024
        ns = torch.arange(S)[:, None] * torch.arange(S)[None, :]
        nd = torch.arange(D)[:, None] * torch.arange(D)[None, :]
        Ws_re = torch.cos(-2.0 * torch.pi * ns / S).to(float)
        Ws_im = torch.sin(-2.0 * torch.pi * ns / S).to(float)
        Wd_re = torch.cos(-2.0 * torch.pi * nd / D).to(float)
        Wd_im = torch.sin(-2.0 * torch.pi * nd / D).to(float)
        return {
            "x": _w((lambda *s: torch.randn(*s, dtype=torch.bfloat16) * 0.05)(B, S, D)),
            "dft_seq_re": _w(Ws_re),
            "dft_seq_im": _w(Ws_im),
            "dft_hid_re": _w(Wd_re),
            "dft_hid_im": _w(Wd_im),
        }
    _A_in = _A_setup()

    def _B_setup():
        B, S, D, F = 1, 2048, 1024, 3584
        return {
            "x": _w((lambda *s: torch.randn(*s, dtype=torch.bfloat16) * 0.05)(B, S, D)),
            "w_gate": _w((lambda *s: torch.randn(*s, dtype=torch.bfloat16) * 1.6)(D, F)),
            "w_up": _w((lambda *s: torch.randn(*s, dtype=torch.bfloat16) * 0.8)(D, F)),
            "w_down": _w((lambda *s: torch.randn(*s, dtype=torch.bfloat16) * 0.8)(F, D)),
        }
    _B_in = _B_setup()

    return {
        "A_x": _A_in["x"],
        "A_dft_seq_re": _A_in["dft_seq_re"],
        "A_dft_seq_im": _A_in["dft_seq_im"],
        "A_dft_hid_re": _A_in["dft_hid_re"],
        "A_dft_hid_im": _A_in["dft_hid_im"],
        "B_x": _B_in["x"],
        "B_w_gate": _B_in["w_gate"],
        "B_w_up": _B_in["w_up"],
        "B_w_down": _B_in["w_down"],
        "gate_w": _w((lambda *s: torch.randn(*s, dtype=torch.bfloat16) * 0.05)(1024) * 16.0),
    }

def reference(A_x, A_dft_seq_re, A_dft_seq_im, A_dft_hid_re, A_dft_hid_im, B_x, B_w_gate, B_w_up, B_w_down, gate_w):
    def _A_ref(x, dft_seq_re, dft_seq_im, dft_hid_re, dft_hid_im):
        a = torch.einsum("bsd,ed->bse", x, dft_hid_re)
        b = torch.einsum("bsd,ed->bse", x, dft_hid_im)
        y = torch.einsum("ts,bse->bte", dft_seq_re, a) - torch.einsum("ts,bse->bte", dft_seq_im, b)
        return y

    def _B_ref(x, w_gate, w_up, w_down):
        g = torch.einsum("bsd,df->bsf", x, w_gate)
        u = torch.einsum("bsd,df->bsf", x, w_up)
        h = _sigmoid(g) * u
        return torch.einsum("bsf,fd->bsd", h, w_down)

    x = A_x
    g = _sigmoid((x * gate_w).sum(-1, keepdims=True))
    a = _A_ref(x, A_dft_seq_re, A_dft_seq_im, A_dft_hid_re, A_dft_hid_im)
    b = _B_ref(x, B_w_gate, B_w_up, B_w_down)
    return g * a + (1 - g) * b
```

```cpp
#include <cuda_runtime.h>
#include <cuda_bf16.h>
#include <cuda.h>
#include <stdint.h>

namespace {

constexpr int SEQ = 2048, DM = 1024, FF = 3584, KH = 2 * DM + FF;
constexpr int STAGES = 4;
constexpr int A_BYTES = 128 * 64 * 2, B_BYTES = 256 * 64 * 2, STG_BYTES = A_BYTES + B_BYTES;
constexpr int CH_BYTES = 64 * 64 * 2;
constexpr int OFF_STAGING = STAGES * STG_BYTES;
constexpr int OFF_GBUF = OFF_STAGING + 4 * CH_BYTES;
constexpr int OFF_BARS = OFF_GBUF + 512;
constexpr int BAR_FULL = 0, BAR_EMPTY = STAGES, BAR_SFULL = 2 * STAGES, BAR_SEMPTY = BAR_SFULL + 4,
              BAR_GREADY = BAR_SEMPTY + 4, NBARS = BAR_GREADY + 2;
constexpr int SMEM_BYTES = OFF_BARS + NBARS * 8 + 1024;

constexpr int T_PQ = 0, T_GU = 1, T_OUT = 2;
constexpr int NTILE1 = 36;
constexpr int FLAG_GATE = 16 * NTILE1, FLAG_ZERO = FLAG_GATE + 16, NFLAGS = FLAG_ZERO + 1;
constexpr int MAX_ITEMS = 384, MAX_CLUSTERS = 66;
constexpr int SPIN_LIMIT = 1 << 22;

enum { M_CSRE, M_CSIM, M_XA, M_XB, M_WG, M_WU, M_HA, M_HS, M_CDRE, M_CDIM, M_WD, M_OUT, NMAPS };

struct alignas(64) Params {
    CUtensorMap maps[NMAPS];
    const __nv_bfloat16* x;
    const __nv_bfloat16* gate_w;
    __nv_bfloat16* out;
    uint32_t items[MAX_ITEMS];
    uint16_t off[MAX_CLUSTERS + 2];
};

__device__ __align__(1024) __nv_bfloat16 g_H[(size_t)SEQ * KH];
__device__ __align__(16) uint32_t g_gate[SEQ];
__device__ uint32_t g_flags[NFLAGS];
__device__ uint32_t g_exit;

__host__ __device__ constexpr uint32_t mk_item(int type, int rp, int col, int kbeg, int nks) {
    return (uint32_t)type | ((uint32_t)rp << 2) | ((uint32_t)col << 5) | ((uint32_t)kbeg << 10) | ((uint32_t)nks << 17);
}
__device__ __forceinline__ int it_type(uint32_t v) { return v & 3; }
__device__ __forceinline__ int it_rp(uint32_t v) { return (v >> 2) & 7; }
__device__ __forceinline__ int it_col(uint32_t v) { return (v >> 5) & 31; }
__device__ __forceinline__ int it_kbeg(uint32_t v) { return (v >> 10) & 127; }
__device__ __forceinline__ int it_nks(uint32_t v) { return (v >> 17) & 127; }

__device__ __forceinline__ uint32_t smem_u32(const void* p) { return (uint32_t)__cvta_generic_to_shared(p); }
__device__ __forceinline__ void mbar_init(uint32_t bar, uint32_t cnt) {
    asm volatile("mbarrier.init.shared::cta.b64 [%0], %1;" ::"r"(bar), "r"(cnt) : "memory");
}
__device__ __forceinline__ void mbar_expect_tx(uint32_t bar, uint32_t bytes) {
    asm volatile("mbarrier.arrive.expect_tx.shared::cta.b64 _, [%0], %1;" ::"r"(bar), "r"(bytes) : "memory");
}
__device__ __forceinline__ void mbar_arrive(uint32_t bar) {
    asm volatile("mbarrier.arrive.shared::cta.b64 _, [%0];" ::"r"(bar) : "memory");
}
__device__ __forceinline__ void mbar_arrive_cluster(uint32_t cluster_addr) {
    asm volatile("mbarrier.arrive.shared::cluster.b64 _, [%0];" ::"r"(cluster_addr) : "memory");
}
__device__ __forceinline__ uint32_t mapa(uint32_t addr, uint32_t cta) {
    uint32_t r;
    asm("mapa.shared::cluster.u32 %0, %1, %2;" : "=r"(r) : "r"(addr), "r"(cta));
    return r;
}
__device__ __forceinline__ void fail_hard() { asm volatile("st.global.u32 [%0], %1;" ::"l"(0ull), "r"(0) : "memory"); }
__device__ __forceinline__ bool mbar_try(uint32_t bar, uint32_t parity) {
    uint32_t ok;
    asm volatile("{.reg .pred p; mbarrier.try_wait.parity.shared::cta.b64 p, [%1], %2; selp.u32 %0,1,0,p;}"
                 : "=r"(ok) : "r"(bar), "r"(parity) : "memory");
    return ok;
}
__device__ __forceinline__ void mbar_wait(uint32_t bar, uint32_t parity) {
    if (mbar_try(bar, parity)) return;
    int it = 0;
    while (!mbar_try(bar, parity))
        if (++it > SPIN_LIMIT) fail_hard();
}
__device__ __forceinline__ bool elect_one() {
    uint32_t p;
    asm volatile("{.reg .pred p; elect.sync _|p, 0xffffffff; selp.u32 %0,1,0,p;}" : "=r"(p));
    return p;
}
__device__ __forceinline__ void wg_fence() { asm volatile("wgmma.fence.sync.aligned;" ::: "memory"); }
__device__ __forceinline__ void wg_commit() { asm volatile("wgmma.commit_group.sync.aligned;" ::: "memory"); }
template <int N> __device__ __forceinline__ void wg_wait() {
    asm volatile("wgmma.wait_group.sync.aligned %0;" ::"n"(N) : "memory");
}
__device__ __forceinline__ uint64_t make_desc(uint32_t addr, uint32_t lbo, uint32_t sbo) {
    return (uint64_t)((addr & 0x3FFFF) >> 4) | ((uint64_t)(lbo >> 4) << 16) | ((uint64_t)(sbo >> 4) << 32) | (1ull << 62);
}
#define R8(a, i) "+f"(a[i]), "+f"(a[i + 1]), "+f"(a[i + 2]), "+f"(a[i + 3]), "+f"(a[i + 4]), "+f"(a[i + 5]), "+f"(a[i + 6]), "+f"(a[i + 7])
template <int TB>
__device__ __forceinline__ void wgmma256(float (&d)[128], uint64_t da, uint64_t db, int scale_d) {
    asm volatile(
        "{.reg .pred p; setp.ne.b32 p, %130, 0;\n"
        "wgmma.mma_async.sync.aligned.m64n256k16.f32.bf16.bf16 "
        "{%0,%1,%2,%3,%4,%5,%6,%7,%8,%9,%10,%11,%12,%13,%14,%15,%16,%17,%18,%19,%20,%21,%22,%23,%24,%25,%26,%27,%28,%29,%30,%31,"
        "%32,%33,%34,%35,%36,%37,%38,%39,%40,%41,%42,%43,%44,%45,%46,%47,%48,%49,%50,%51,%52,%53,%54,%55,%56,%57,%58,%59,%60,%61,%62,%63,"
        "%64,%65,%66,%67,%68,%69,%70,%71,%72,%73,%74,%75,%76,%77,%78,%79,%80,%81,%82,%83,%84,%85,%86,%87,%88,%89,%90,%91,%92,%93,%94,%95,"
        "%96,%97,%98,%99,%100,%101,%102,%103,%104,%105,%106,%107,%108,%109,%110,%111,%112,%113,%114,%115,%116,%117,%118,%119,%120,%121,%122,%123,%124,%125,%126,%127},"
        "%128, %129, p, 1, 1, 0, %131;}\n"
        : R8(d, 0), R8(d, 8), R8(d, 16), R8(d, 24), R8(d, 32), R8(d, 40), R8(d, 48), R8(d, 56), R8(d, 64), R8(d, 72),
          R8(d, 80), R8(d, 88), R8(d, 96), R8(d, 104), R8(d, 112), R8(d, 120)
        : "l"(da), "l"(db), "r"(scale_d), "n"(TB));
}
__device__ __forceinline__ void tma_ld(uint32_t dst, const CUtensorMap* m, int c0, int c1, int c2, uint32_t bar) {
    asm volatile("cp.async.bulk.tensor.3d.shared::cluster.global.mbarrier::complete_tx::bytes [%0], [%1,{%2,%3,%4}], [%5];"
                 ::"r"(dst), "l"(m), "r"(c0), "r"(c1), "r"(c2), "r"(bar) : "memory");
}
__device__ __forceinline__ void tma_ld_mc(uint32_t dst, const CUtensorMap* m, int c0, int c1, int c2, uint32_t bar) {
    asm volatile("cp.async.bulk.tensor.3d.shared::cluster.global.mbarrier::complete_tx::bytes.multicast::cluster [%0], [%1,{%2,%3,%4}], [%5], %6;"
                 ::"r"(dst), "l"(m), "r"(c0), "r"(c1), "r"(c2), "r"(bar), "h"((uint16_t)3) : "memory");
}
__device__ __forceinline__ void tma_st(const CUtensorMap* m, int c0, int c1, uint32_t src) {
    asm volatile("cp.async.bulk.tensor.3d.global.shared::cta.bulk_group [%0,{%1,%2,%3}], [%4];"
                 ::"l"(m), "r"(c0), "r"(c1), "r"(0), "r"(src) : "memory");
}
__device__ __forceinline__ void tma_red(const CUtensorMap* m, int c0, int c1, uint32_t src) {
    asm volatile("cp.reduce.async.bulk.tensor.3d.global.shared::cta.add.bulk_group [%0,{%1,%2,%3}], [%4];"
                 ::"l"(m), "r"(c0), "r"(c1), "r"(0), "r"(src) : "memory");
}
__device__ __forceinline__ void bulk_commit() { asm volatile("cp.async.bulk.commit_group;" ::: "memory"); }
template <int N> __device__ __forceinline__ void bulk_wait_read() {
    asm volatile("cp.async.bulk.wait_group.read %0;" ::"n"(N) : "memory");
}
template <int N> __device__ __forceinline__ void bulk_wait() {
    asm volatile("cp.async.bulk.wait_group %0;" ::"n"(N) : "memory");
}
__device__ __forceinline__ void fence_async_smem() { asm volatile("fence.proxy.async.shared::cta;" ::: "memory"); }
__device__ __forceinline__ void fence_async_global() { asm volatile("fence.proxy.async.global;" ::: "memory"); }
__device__ __forceinline__ uint32_t ld_acquire(const uint32_t* p) {
    uint32_t v;
    asm volatile("ld.acquire.gpu.global.u32 %0, [%1];" : "=r"(v) : "l"(p) : "memory");
    return v;
}
__device__ __forceinline__ void red_release(uint32_t* p, uint32_t v) {
    asm volatile("red.release.gpu.global.add.u32 [%0], %1;" ::"l"(p), "r"(v) : "memory");
}
__device__ __forceinline__ void poll_ge(const uint32_t* p, uint32_t target) {
    int it = 0;
    while (ld_acquire(p) < target) {
        __nanosleep(64);
        if (++it > SPIN_LIMIT) fail_hard();
    }
}
__device__ __forceinline__ void stsm4(uint32_t addr, uint32_t r0, uint32_t r1, uint32_t r2, uint32_t r3) {
    asm volatile("stmatrix.sync.aligned.m8n8.x4.shared.b16 [%0], {%1,%2,%3,%4};"
                 ::"r"(addr), "r"(r0), "r"(r1), "r"(r2), "r"(r3) : "memory");
}
__device__ __forceinline__ uint32_t pack_bf16(float lo, float hi) {
    uint32_t r;
    asm("cvt.rn.bf16x2.f32 %0, %1, %2;" : "=r"(r) : "f"(hi), "f"(lo));
    return r;
}
__device__ __forceinline__ float bf_lo(uint32_t v) { return __uint_as_float(v << 16); }
__device__ __forceinline__ float bf_hi(uint32_t v) { return __uint_as_float(v & 0xffff0000u); }
__device__ __forceinline__ float sigmoid_fast(float v) {
    float e, r;
    asm("ex2.approx.ftz.f32 %0, %1;" : "=f"(e) : "f"(v * -1.4426950408889634f));
    asm("rcp.approx.ftz.f32 %0, %1;" : "=f"(r) : "f"(1.0f + e));
    return r;
}
__device__ __forceinline__ uint32_t glu_pair(uint32_t g, uint32_t u, float sc) {
    return pack_bf16(bf_lo(u) * sc * sigmoid_fast(bf_lo(g)), bf_hi(u) * sc * sigmoid_fast(bf_hi(g)));
}

struct Epi {
    int pend;
    int gu;
    int cc;
    float sc0, sc1;
};
__device__ __forceinline__ void epi_step(Epi& e, const uint32_t (&pk)[64], uint32_t stg_addr, uint32_t swz, uint32_t bars,
                                         int wg, int lane) {
    const int sub = 8 - e.pend;
    const int buf = e.cc & 1;
    const uint32_t dst = stg_addr + buf * CH_BYTES;
    const int lastm = e.gu ? 3 : 1;
    const int pos = sub & lastm;
    if (pos == 0) mbar_wait(bars + (BAR_SEMPTY + wg * 2 + buf) * 8, ((e.cc >> 1) & 1) ^ 1);
    uint32_t t[8];
#define EPI_CASE(n) case n: _Pragma("unroll") for (int q = 0; q < 8; q++) t[q] = pk[n * 8 + q]; break;
    switch (sub) {
        EPI_CASE(0) EPI_CASE(1) EPI_CASE(2) EPI_CASE(3) EPI_CASE(4) EPI_CASE(5) EPI_CASE(6)
        default: _Pragma("unroll") for (int q = 0; q < 8; q++) t[q] = pk[56 + q]; break;
    }
#undef EPI_CASE
    if (e.gu) {
        uint32_t o0 = glu_pair(t[0], t[4], e.sc0), o1 = glu_pair(t[1], t[5], e.sc1);
        uint32_t o2 = glu_pair(t[2], t[6], e.sc0), o3 = glu_pair(t[3], t[7], e.sc1);
        stsm4(dst + (swz ^ (pos << 5)), o0, o1, o2, o3);
    } else {
        stsm4(dst + (swz ^ (pos << 6)), t[0], t[1], t[2], t[3]);
        stsm4(dst + (swz ^ ((pos << 6) | 32)), t[4], t[5], t[6], t[7]);
    }
    if (pos == lastm) {
        fence_async_smem();
        __syncwarp();
        if (lane == 0) mbar_arrive(bars + (BAR_SFULL + wg * 2 + buf) * 8);
        e.cc++;
    }
    e.pend--;
}

__global__ void __cluster_dims__(2, 1, 1) __launch_bounds__(384, 1)
fused_kernel(const __grid_constant__ Params P) {
    extern __shared__ uint8_t smem_raw[];
    const uint32_t base = (smem_u32(smem_raw) + 1023) & ~1023u;
    const uint32_t bars = base + OFF_BARS;
    const int warp = threadIdx.x >> 5, lane = threadIdx.x & 31;
    uint32_t rank;
    asm("mov.u32 %0, %%cluster_ctarank;" : "=r"(rank));
    const int cl = blockIdx.x >> 1;
    const int it0 = P.off[cl], it1 = P.off[cl + 1];

    if (warp == 8 && lane < NMAPS)
        asm volatile("prefetch.tensormap [%0];" ::"l"(&P.maps[lane]) : "memory");
    if (warp == 9 && lane == 0) {
        for (int s = 0; s < STAGES; s++) {
            mbar_init(bars + (BAR_FULL + s) * 8, 1);
            mbar_init(bars + (BAR_EMPTY + s) * 8, 16);
        }
        for (int s = 0; s < 4; s++) {
            mbar_init(bars + (BAR_SFULL + s) * 8, 4);
            mbar_init(bars + (BAR_SEMPTY + s) * 8, 1);
        }
        mbar_init(bars + (BAR_GREADY + 0) * 8, 1);
        mbar_init(bars + (BAR_GREADY + 1) * 8, 1);
        asm volatile("fence.mbarrier_init.release.cluster;" ::: "memory");
    }
    __syncwarp();
    asm volatile("barrier.cluster.arrive.relaxed.aligned;" ::: "memory");

    if (warp >= 8) {
        asm volatile("setmaxnreg.dec.sync.aligned.u32 40;");
        asm volatile("barrier.cluster.wait.aligned;" ::: "memory");
        asm volatile("barrier.cluster.arrive.relaxed.aligned;" ::: "memory");
        if (warp == 8) {
            int s = 0;
            uint32_t ph = 1;
            for (int it = it0; it < it1; it++) {
                const uint32_t v = P.items[it];
                const int type = it_type(v), col = it_col(v), nks = it_nks(v);
                const int rb = it_rp(v) * 2 + rank;
                int k = it_kbeg(v);
                const CUtensorMap* mA = &P.maps[type == T_PQ ? (col < 4 ? M_CSRE : M_CSIM) : (type == T_GU ? M_XA : M_HA)];
                const CUtensorMap* mB = &P.maps[type == T_PQ ? M_XB : (rank ? M_WU : M_WG)];
                int b0 = 0, b1 = 0, b2 = type == T_PQ ? (col & 3) * 4 + rank * 2 : col * 2;
                uint32_t ready = 0;
                for (int i = 0; i < nks; i++, k++) {
                    if (type == T_OUT) {
                        if (k < 32) {
                            mB = &P.maps[k < 16 ? M_CDRE : M_CDIM];
                            b0 = (k & 15) * 64; b1 = col * 256 + rank * 128; b2 = 0;
                        } else {
                            mB = &P.maps[M_WD];
                            b0 = 0; b1 = (k - 32) * 64; b2 = col * 4 + rank * 2;
                        }
                        if (!(ready & 1)) {
                            const int kk = min(k + lane, 87);
                            const uint32_t* f = &g_flags[rb * NTILE1 + (kk < 32 ? (kk >> 2) : 8 + ((kk - 32) >> 1))];
                            int spin = 0;
                            while (true) {
                                ready = __ballot_sync(0xffffffffu, ld_acquire(f) >= 2);
                                if (ready & 1) break;
                                __nanosleep(32);
                                if (++spin > SPIN_LIMIT) fail_hard();
                            }
                            __syncwarp();
                            fence_async_global();
                        }
                        ready >>= 1;
                    } else {
                        b1 = k * 64;
                    }
                    mbar_wait(bars + (BAR_EMPTY + s) * 8, ph);
                    if (elect_one()) {
                        const uint32_t full = bars + (BAR_FULL + s) * 8;
                        const uint32_t a = base + s * STG_BYTES;
                        mbar_expect_tx(full, STG_BYTES);
                        tma_ld(a, mA, k * 64, rb * 128, 0, full);
                        tma_ld_mc(a + A_BYTES + rank * (B_BYTES / 2), mB, b0, b1, b2, full);
                    }
                    __syncwarp();
                    if (++s == STAGES) { s = 0; ph ^= 1; }
                }
            }
            asm volatile("bar.arrive 2, 128;" ::: "memory");
        } else if (warp < 11) {
            const int w = warp - 9;
            int np1 = 0;
            while (it0 + np1 < it1 && it_type(P.items[it0 + np1]) != T_OUT) np1++;
            const int zi = min(2, np1 - 1);
            int cc = 0;
            for (int j = -1; j < it1 - it0; j++) {
                if (j >= 0) {
                    const uint32_t v = P.items[it0 + j];
                    const int type = it_type(v), col = it_col(v);
                    const int rb = it_rp(v) * 2 + rank;
                    const int nch = type == T_GU ? 2 : 4;
                    const int c0 = type == T_GU ? 2 * DM + col * 128 : col * 256;
                    for (int c = 0; c < nch; c++, cc++) {
                        const int buf = cc & 1;
                        mbar_wait(bars + (BAR_SFULL + w * 2 + buf) * 8, (cc >> 1) & 1);
                        if (lane == 0) {
                            const uint32_t src = base + OFF_STAGING + (w * 2 + buf) * CH_BYTES;
                            if (type == T_OUT) tma_red(&P.maps[M_OUT], c0 + c * 64, rb * 128 + w * 64, src);
                            else tma_st(&P.maps[M_HS], c0 + c * 64, rb * 128 + w * 64, src);
                            bulk_commit();
                            if (c > 0) {
                                bulk_wait_read<1>();
                                mbar_arrive(bars + (BAR_SEMPTY + w * 2 + (buf ^ 1)) * 8);
                            }
                        }
                        __syncwarp();
                    }
                    if (lane == 0) {
                        bulk_wait<0>();
                        mbar_arrive(bars + (BAR_SEMPTY + w * 2 + ((cc - 1) & 1)) * 8);
                        if (type != T_OUT) {
                            fence_async_global();
                            red_release(&g_flags[rb * NTILE1 + (type == T_GU ? 8 + col : col)], 1);
                        }
                    }
                    __syncwarp();
                }
                if (j + 1 < np1) {
                    const uint32_t v = P.items[it0 + j + 1];
                    const int rb = it_rp(v) * 2 + rank;
                    poll_ge(&g_flags[FLAG_GATE + rb], 8);
                    const uint2 gg = __ldcg(reinterpret_cast<const uint2*>(&g_gate[rb * 128 + w * 64 + lane * 2]));
                    float s0, s1;
                    if (it_type(v) == T_GU) { s0 = bf_hi(gg.x); s1 = bf_hi(gg.y); }
                    else if (it_col(v) < 4) { s0 = bf_lo(gg.x); s1 = bf_lo(gg.y); }
                    else { s0 = -bf_lo(gg.x); s1 = -bf_lo(gg.y); }
                    asm volatile("st.shared.v2.f32 [%0], {%1,%2};" ::"r"(base + OFF_GBUF + (w * 64 + lane * 2) * 4), "f"(s0), "f"(s1) : "memory");
                    __syncwarp();
                    if (lane == 0) mbar_arrive(bars + (BAR_GREADY + w) * 8);
                }
                if (j == zi) {
                    uint4* o = reinterpret_cast<uint4*>(P.out);
                    for (int i = (blockIdx.x * 2 + w) * 32 + lane; i < SEQ * DM / 8; i += gridDim.x * 64)
                        o[i] = make_uint4(0, 0, 0, 0);
                    __syncwarp();
                    if (lane == 0) red_release(&g_flags[FLAG_ZERO], 1);
                }
                if (j == np1 - 1) {
                    poll_ge(&g_flags[FLAG_ZERO], gridDim.x * 2);
                    fence_async_global();
                    asm volatile("bar.arrive 2, 128;" ::: "memory");
                }
            }
        } else {
            for (int r0 = blockIdx.x * 16; r0 < SEQ; r0 += gridDim.x * 16) {
                asm volatile("bar.sync 1, 288;" ::: "memory");
                if (lane == 0) red_release(&g_flags[FLAG_GATE + (r0 >> 7)], 1);
                __syncwarp();
                if (r0 + gridDim.x * 16 < SEQ) asm volatile("bar.arrive 3, 288;" ::: "memory");
            }
            asm volatile("bar.sync 2, 128;" ::: "memory");
            uint32_t old = 0;
            if (lane == 0)
                asm volatile("atom.acq_rel.gpu.global.inc.u32 %0, [%1], %2;" : "=r"(old) : "l"(&g_exit), "r"(gridDim.x - 1) : "memory");
            old = __shfl_sync(0xffffffffu, old, 0);
            if (old == gridDim.x - 1)
                for (int i = lane; i < NFLAGS; i += 32) g_flags[i] = 0;
        }
        asm volatile("barrier.cluster.wait.aligned;" ::: "memory");
    } else {
        asm volatile("setmaxnreg.inc.sync.aligned.u32 232;");
        const int wg = warp >> 2;
        for (int r0 = blockIdx.x * 16; r0 < SEQ; r0 += gridDim.x * 16) {
            const uint4* xr = reinterpret_cast<const uint4*>(P.x + (size_t)(r0 + warp * 2) * DM);
            const uint4* gw = reinterpret_cast<const uint4*>(P.gate_w);
            uint4 xa[4], xb[4], w4[4];
#pragma unroll
            for (int q = 0; q < 4; q++) {
                xa[q] = __ldg(xr + q * 32 + lane);
                xb[q] = __ldg(xr + 128 + q * 32 + lane);
                w4[q] = __ldg(gw + q * 32 + lane);
            }
            float za = 0.f, zb = 0.f;
#pragma unroll
            for (int q = 0; q < 4; q++) {
                const uint32_t* pa = reinterpret_cast<const uint32_t*>(&xa[q]);
                const uint32_t* pb = reinterpret_cast<const uint32_t*>(&xb[q]);
                const uint32_t* pw = reinterpret_cast<const uint32_t*>(&w4[q]);
#pragma unroll
                for (int e = 0; e < 4; e++) {
                    uint32_t ma, mb;
                    asm("mul.rn.bf16x2 %0, %1, %2;" : "=r"(ma) : "r"(pa[e]), "r"(pw[e]));
                    asm("mul.rn.bf16x2 %0, %1, %2;" : "=r"(mb) : "r"(pb[e]), "r"(pw[e]));
                    za += bf_lo(ma) + bf_hi(ma);
                    zb += bf_lo(mb) + bf_hi(mb);
                }
            }
#pragma unroll
            for (int o = 16; o > 0; o >>= 1) {
                za += __shfl_xor_sync(0xffffffffu, za, o);
                zb += __shfl_xor_sync(0xffffffffu, zb, o);
            }
            if (lane < 2) {
                const float z = __bfloat162float(__float2bfloat16(lane ? zb : za));
                const float g = __bfloat162float(__float2bfloat16(1.0f / (1.0f + __expf(-z))));
                g_gate[r0 + warp * 2 + lane] = pack_bf16(g, 1.0f - g);
            }
            __syncwarp();
            asm volatile("bar.arrive 1, 288;" ::: "memory");
            if (r0 + gridDim.x * 16 < SEQ) asm volatile("bar.sync 3, 288;" ::: "memory");
        }
        asm volatile("barrier.cluster.wait.aligned;" ::: "memory");

        float acc[128];
        uint32_t pk[64];
#pragma unroll
        for (int i = 0; i < 128; i++) acc[i] = 0.f;
#pragma unroll
        for (int i = 0; i < 64; i++) pk[i] = 0;
        Epi e;
        e.pend = 0; e.gu = 0; e.cc = 0; e.sc0 = 0.f; e.sc1 = 0.f;
        const int srow = (warp & 3) * 16 + ((lane >> 3) & 1) * 8 + (lane & 7);
        const uint32_t stg_addr = base + OFF_STAGING + wg * 2 * CH_BYTES + srow * 128;
        const uint32_t swz = (uint32_t)(((lane >> 4) ^ (lane & 7)) << 4);
        const uint32_t empty_remote = mapa(bars + BAR_EMPTY * 8, lane & 1);
        int s = 0, gph = 0;
        uint32_t ph = 0;
        for (int it = it0; it < it1; it++) {
            const uint32_t v = P.items[it];
            const int type = it_type(v), nks = it_nks(v);
            const int nkm = type == T_OUT ? 32 - it_kbeg(v) : 0;
            int ps = 0;
            for (int i = 0; i < nks; i++) {
                mbar_wait(bars + (BAR_FULL + s) * 8, ph);
                const uint32_t a = base + s * STG_BYTES + wg * (A_BYTES / 2), b = base + s * STG_BYTES + A_BYTES;
                const uint64_t da = make_desc(a, 16, 1024);
                if (i < nkm) {
                    const uint64_t db = make_desc(b, 16, 1024);
                    wg_fence();
                    wgmma256<0>(acc, da, db, i);
                    wgmma256<0>(acc, da + 2, db + 2, 1);
                    wgmma256<0>(acc, da + 4, db + 4, 1);
                    wgmma256<0>(acc, da + 6, db + 6, 1);
                    wg_commit();
                } else {
                    const uint64_t db = make_desc(b, 8192, 1024);
                    wg_fence();
                    wgmma256<1>(acc, da, db, i);
                    wgmma256<1>(acc, da + 2, db + 128, 1);
                    wgmma256<1>(acc, da + 4, db + 256, 1);
                    wgmma256<1>(acc, da + 6, db + 384, 1);
                    wg_commit();
                }
                wg_wait<1>();
                if (i > 0 && lane < 2) mbar_arrive_cluster(empty_remote + ps * 8);
                if (e.pend) epi_step(e, pk, stg_addr, swz, bars, wg, lane);
                ps = s;
                if (++s == STAGES) { s = 0; ph ^= 1; }
            }
            float sc0 = 1.f, sc1 = 1.f;
            if (type != T_OUT) {
                mbar_wait(bars + (BAR_GREADY + wg) * 8, gph);
                gph ^= 1;
                const uint32_t ga = base + OFF_GBUF + (wg * 64 + (warp & 3) * 16 + (lane >> 2)) * 4;
                asm volatile("ld.shared.f32 %0, [%1];" : "=f"(sc0) : "r"(ga) : "memory");
                asm volatile("ld.shared.f32 %0, [%1+32];" : "=f"(sc1) : "r"(ga) : "memory");
            }
            wg_wait<0>();
            if (lane < 2) mbar_arrive_cluster(empty_remote + ps * 8);
            if (type == T_GU) {
#pragma unroll
                for (int j = 0; j < 8; j++) {
#pragma unroll
                    for (int q = 0; q < 4; q++) {
                        pk[j * 8 + q] = pack_bf16(acc[j * 8 + q * 2], acc[j * 8 + q * 2 + 1]);
                        pk[j * 8 + 4 + q] = pack_bf16(acc[64 + j * 8 + q * 2], acc[64 + j * 8 + q * 2 + 1]);
                    }
                }
                e.gu = 1; e.sc0 = sc0; e.sc1 = sc1;
            } else {
#pragma unroll
                for (int j = 0; j < 32; j++) {
                    pk[j * 2] = pack_bf16(acc[j * 4] * sc0, acc[j * 4 + 1] * sc0);
                    pk[j * 2 + 1] = pack_bf16(acc[j * 4 + 2] * sc1, acc[j * 4 + 3] * sc1);
                }
                e.gu = 0;
            }
            e.pend = 8;
        }
        asm volatile("barrier.cluster.arrive.relaxed.aligned;" ::: "memory");
        while (e.pend) epi_step(e, pk, stg_addr, swz, bars, wg, lane);
        asm volatile("barrier.cluster.wait.aligned;" ::: "memory");
    }
}

typedef CUresult (*EncFn)(CUtensorMap*, CUtensorMapDataType, cuuint32_t, void*, const cuuint64_t*, const cuuint64_t*,
                          const cuuint32_t*, const cuuint32_t*, CUtensorMapInterleave, CUtensorMapSwizzle,
                          CUtensorMapL2promotion, CUtensorMapFloatOOBfill);

void enc3(EncFn f, CUtensorMap* m, const void* p, uint64_t d0, uint64_t d1, uint64_t d2, uint64_t s1, uint64_t s2,
          uint32_t b0, uint32_t b1, uint32_t b2) {
    cuuint64_t gd[3] = {d0, d1, d2};
    cuuint64_t gs[2] = {s1, s2};
    cuuint32_t bd[3] = {b0, b1, b2};
    cuuint32_t es[3] = {1, 1, 1};
    f(m, CU_TENSOR_MAP_DATA_TYPE_BFLOAT16, 3, const_cast<void*>(p), gd, gs, bd, es, CU_TENSOR_MAP_INTERLEAVE_NONE,
      CU_TENSOR_MAP_SWIZZLE_128B, CU_TENSOR_MAP_L2_PROMOTION_L2_128B, CU_TENSOR_MAP_FLOAT_OOB_FILL_NONE);
}
void enc_rowmajor(EncFn f, CUtensorMap* m, const void* p, int rows, int cols, int brows) {
    enc3(f, m, p, cols, rows, 1, (uint64_t)cols * 2, (uint64_t)cols * 2 * rows, 64, brows, 1);
}
void enc_nmajor(EncFn f, CUtensorMap* m, const void* p, int krows, int cols) {
    enc3(f, m, p, 64, krows, cols / 64, (uint64_t)cols * 2, 128, 64, 64, 2);
}

int build_schedule(Params& P, int max_clusters) {
    int n = 0, ncl;
    if (max_clusters >= 64) {
        ncl = 64;
        for (int c = 0; c < ncl; c++) {
            const int r = c & 7, j = c >> 3;
            P.off[c] = n;
            P.items[n++] = mk_item(T_PQ, r, j, 0, 32);
            for (int q = 0; q < (j < 4 ? 4 : 3); q++) P.items[n++] = mk_item(T_GU, r, q * 8 + j, 0, 16);
            P.items[n++] = j < 4 ? mk_item(T_OUT, r, j, 52, 36) : mk_item(T_OUT, r, j - 4, 0, 52);
        }
    } else {
        ncl = max_clusters < 1 ? 1 : max_clusters;
        for (int c = 0; c < ncl; c++) {
            P.off[c] = n;
            for (int t = c; t < 8 * NTILE1; t += ncl) {
                const int r = t & 7, j = t >> 3;
                P.items[n++] = j < 8 ? mk_item(T_PQ, r, j, 0, 32) : mk_item(T_GU, r, j - 8, 0, 16);
            }
            for (int t = c; t < 32; t += ncl) P.items[n++] = mk_item(T_OUT, t & 7, t >> 3, 0, 88);
        }
    }
    P.off[ncl] = n;
    return ncl;
}

}

extern "C" void kernel_launch(void* const* d_in, const int* in_sizes, int n_in, void* d_out, int out_size) {
    static Params P;
    static int ncl = 0;
    static const void* key[11];
    bool same = ncl > 0;
    for (int i = 0; i < 10; i++) same = same && key[i] == d_in[i];
    same = same && key[10] == d_out;
    if (!same) {
        for (int i = 0; i < 10; i++) key[i] = d_in[i];
        key[10] = d_out;
        EncFn f = nullptr;
        cudaDriverEntryPointQueryResult q;
        cudaGetDriverEntryPoint("cuTensorMapEncodeTiled", (void**)&f, cudaEnableDefault, &q);
        void* H = nullptr;
        cudaGetSymbolAddress(&H, g_H);
        enc_rowmajor(f, &P.maps[M_CSRE], d_in[1], SEQ, SEQ, 128);
        enc_rowmajor(f, &P.maps[M_CSIM], d_in[2], SEQ, SEQ, 128);
        enc_rowmajor(f, &P.maps[M_XA], d_in[0], SEQ, DM, 128);
        enc_nmajor(f, &P.maps[M_XB], d_in[0], SEQ, DM);
        enc_nmajor(f, &P.maps[M_WG], d_in[6], DM, FF);
        enc_nmajor(f, &P.maps[M_WU], d_in[7], DM, FF);
        enc_rowmajor(f, &P.maps[M_HA], H, SEQ, KH, 128);
        enc_rowmajor(f, &P.maps[M_HS], H, SEQ, KH, 64);
        enc_rowmajor(f, &P.maps[M_CDRE], d_in[3], DM, DM, 128);
        enc_rowmajor(f, &P.maps[M_CDIM], d_in[4], DM, DM, 128);
        enc_nmajor(f, &P.maps[M_WD], d_in[8], FF, DM);
        enc_rowmajor(f, &P.maps[M_OUT], d_out, SEQ, DM, 64);
        P.x = (const __nv_bfloat16*)d_in[0];
        P.gate_w = (const __nv_bfloat16*)d_in[9];
        P.out = (__nv_bfloat16*)d_out;
        cudaFuncSetAttribute(fused_kernel, cudaFuncAttributeMaxDynamicSharedMemorySize, SMEM_BYTES);
        cudaLaunchConfig_t cfg = {};
        cfg.gridDim = dim3(2 * MAX_CLUSTERS);
        cfg.blockDim = dim3(384);
        cfg.dynamicSmemBytes = SMEM_BYTES;
        cudaLaunchAttribute at[1];
        at[0].id = cudaLaunchAttributeClusterDimension;
        at[0].val.clusterDim.x = 2; at[0].val.clusterDim.y = 1; at[0].val.clusterDim.z = 1;
        cfg.attrs = at;
        cfg.numAttrs = 1;
        int maxc = 0;
        cudaOccupancyMaxActiveClusters(&maxc, fused_kernel, &cfg);
        ncl = build_schedule(P, maxc > MAX_CLUSTERS ? MAX_CLUSTERS : maxc);
    }
    fused_kernel<<<2 * ncl, 384, SMEM_BYTES>>>(P);
}
```

```cpp
#include <cuda_runtime.h>
#include <cuda_bf16.h>
#include <cuda.h>
#include <stdint.h>

namespace {

constexpr int SEQ = 2048, DM = 1024, FF = 3584, KH = 2 * DM + FF;
constexpr int STAGES = 4;
constexpr int A_BYTES = 128 * 64 * 2, B_BYTES = 256 * 64 * 2, STG_BYTES = A_BYTES + B_BYTES;
constexpr int CH_BYTES = 64 * 64 * 2;
constexpr int OFF_STAGING = STAGES * STG_BYTES;
constexpr int OFF_GBUF = OFF_STAGING + 4 * CH_BYTES;
constexpr int OFF_BARS = OFF_GBUF + 512;
constexpr int BAR_FULL = 0, BAR_EMPTY = STAGES, BAR_SFULL = 2 * STAGES, BAR_SEMPTY = BAR_SFULL + 4,
              BAR_GREADY = BAR_SEMPTY + 4, BAR_XROWS = BAR_GREADY + 2, NBARS = BAR_XROWS + 1;
constexpr int SMEM_BYTES = OFF_BARS + NBARS * 8 + 1024;

constexpr int T_PQ = 0, T_GU = 1, T_OUT = 2;
constexpr int NTILE1 = 36;
constexpr int FLAG_GATE = 16 * NTILE1, FLAG_OUT = FLAG_GATE + 16, NFLAGS = FLAG_OUT + 128;
constexpr int MAX_ITEMS = 392, MAX_CLUSTERS = 66;
constexpr uint32_t PACE = 1000;
constexpr int POLL_NS = 64;
constexpr int SPIN_LIMIT = 1 << 20;

enum { M_CSRE, M_CSIM, M_XA, M_XB, M_WG, M_WU, M_HA, M_HS, M_CDRE, M_CDIM, M_WD, M_OUT, NMAPS };

struct alignas(64) Params {
    CUtensorMap maps[NMAPS];
    const __nv_bfloat16* x;
    const __nv_bfloat16* gate_w;
    uint32_t* gate;
    uint32_t* flags;
    uint32_t items[MAX_ITEMS];
    uint16_t off[MAX_CLUSTERS + 2];
};

__device__ __align__(1024) __nv_bfloat16 g_H[(size_t)SEQ * KH];
__device__ __align__(16) uint32_t g_gate[SEQ];
__device__ uint32_t g_flags[NFLAGS + 1];

__host__ __device__ constexpr uint32_t mk_item(int type, int rp, int col, int kbeg, int nks, int first = 0) {
    return (uint32_t)type | ((uint32_t)rp << 2) | ((uint32_t)col << 5) | ((uint32_t)kbeg << 10) | ((uint32_t)nks << 17) |
           ((uint32_t)first << 24);
}
__device__ __forceinline__ int it_type(uint32_t v) { return v & 3; }
__device__ __forceinline__ int it_rp(uint32_t v) { return (v >> 2) & 7; }
__device__ __forceinline__ int it_col(uint32_t v) { return (v >> 5) & 31; }
__device__ __forceinline__ int it_kbeg(uint32_t v) { return (v >> 10) & 127; }
__device__ __forceinline__ int it_nks(uint32_t v) { return (v >> 17) & 127; }
__device__ __forceinline__ int it_first(uint32_t v) { return (v >> 24) & 1; }

__host__ __device__ __forceinline__ int cluster_slot(int c) {
    if (c >= 64) return c;
    const int G = c < 4 ? 15 : c < 36 ? (c - 4) & 7 : 8 + (c - 36) % 7;
    const int m = c < 4 ? c : c < 36 ? (c - 4) >> 3 : (c - 36) / 7;
    return ((G >> 3) * 4 + m) * 8 + (G & 7);
}

__device__ __forceinline__ uint32_t smem_u32(const void* p) { return (uint32_t)__cvta_generic_to_shared(p); }
__device__ __forceinline__ void mbar_init(uint32_t bar, uint32_t cnt) {
    asm volatile("mbarrier.init.shared::cta.b64 [%0], %1;" ::"r"(bar), "r"(cnt) : "memory");
}
__device__ __forceinline__ void mbar_expect_tx(uint32_t bar, uint32_t bytes) {
    asm volatile("mbarrier.arrive.expect_tx.shared::cta.b64 _, [%0], %1;" ::"r"(bar), "r"(bytes) : "memory");
}
__device__ __forceinline__ void mbar_arrive(uint32_t bar) {
    asm volatile("mbarrier.arrive.shared::cta.b64 _, [%0];" ::"r"(bar) : "memory");
}
__device__ __forceinline__ void mbar_arrive_cluster(uint32_t cluster_addr) {
    asm volatile("mbarrier.arrive.shared::cluster.b64 _, [%0];" ::"r"(cluster_addr) : "memory");
}
__device__ __forceinline__ uint32_t mapa(uint32_t addr, uint32_t cta) {
    uint32_t r;
    asm("mapa.shared::cluster.u32 %0, %1, %2;" : "=r"(r) : "r"(addr), "r"(cta));
    return r;
}
__device__ __forceinline__ void fail_hard() { asm volatile("st.global.u32 [%0], %1;" ::"l"(0ull), "r"(0) : "memory"); }
__device__ __forceinline__ bool mbar_test(uint32_t bar, uint32_t parity) {
    uint32_t ok;
    asm volatile("{.reg .pred p; mbarrier.test_wait.parity.shared::cta.b64 p, [%1], %2; selp.u32 %0,1,0,p;}"
                 : "=r"(ok) : "r"(bar), "r"(parity) : "memory");
    return ok;
}
__device__ __forceinline__ int uniform(int v) { return __shfl_sync(0xffffffffu, v, 0); }
template <int I> struct IC { static constexpr int value = I; };
template <int N, int I = 0, class F> __device__ __forceinline__ void static_for(F f) {
    if constexpr (I < N) { f(IC<I>{}); static_for<N, I + 1>(f); }
}
__device__ __forceinline__ void mbar_wait(uint32_t bar, uint32_t parity) {
    asm volatile(
        "{.reg .pred p, q; .reg .b32 n; mov.b32 n, 0;\n"
        "W: mbarrier.try_wait.parity.shared::cta.b64 p, [%0], %1;\n"
        "add.u32 n, n, 1; setp.gt.u32 q, n, %2;\n"
        "@q st.global.u32 [%3], n;\n"
        "@!p bra W;}\n" ::"r"(bar), "r"(parity), "n"(SPIN_LIMIT), "l"(0ull) : "memory");
}
__device__ __forceinline__ void mbar_wait_c(uint32_t bar, uint32_t parity) {
    asm volatile(
        "{.reg .pred p;\n"
        "W: mbarrier.try_wait.parity.shared::cta.b64 p, [%0], %1;\n"
        "@!p bra W;}\n" ::"r"(bar), "r"(parity) : "memory");
}
__device__ __forceinline__ bool elect_one() {
    uint32_t p;
    asm volatile("{.reg .pred p; elect.sync _|p, 0xffffffff; selp.u32 %0,1,0,p;}" : "=r"(p));
    return p;
}
__device__ __forceinline__ void wg_fence() { asm volatile("wgmma.fence.sync.aligned;" ::: "memory"); }
__device__ __forceinline__ void wg_commit() { asm volatile("wgmma.commit_group.sync.aligned;" ::: "memory"); }
template <int N> __device__ __forceinline__ void wg_wait() {
    asm volatile("wgmma.wait_group.sync.aligned %0;" ::"n"(N) : "memory");
}
__device__ __forceinline__ uint32_t desc_lo(uint32_t addr, uint32_t lbo) { return ((addr & 0x3FFFF) >> 4) | ((lbo >> 4) << 16); }
#define R8(a, i) "+f"(a[i]), "+f"(a[i + 1]), "+f"(a[i + 2]), "+f"(a[i + 3]), "+f"(a[i + 4]), "+f"(a[i + 5]), "+f"(a[i + 6]), "+f"(a[i + 7])
template <int TB>
__device__ __forceinline__ void wgmma256(float (&d)[128], uint32_t da, uint32_t db, int scale_d) {
    asm volatile(
        "{.reg .pred p; .reg .b64 da, db; setp.ne.b32 p, %130, 0; mov.b64 da, {%128, 0x40000040}; mov.b64 db, {%129, 0x40000040};\n"
        "wgmma.mma_async.sync.aligned.m64n256k16.f32.bf16.bf16 "
        "{%0,%1,%2,%3,%4,%5,%6,%7,%8,%9,%10,%11,%12,%13,%14,%15,%16,%17,%18,%19,%20,%21,%22,%23,%24,%25,%26,%27,%28,%29,%30,%31,"
        "%32,%33,%34,%35,%36,%37,%38,%39,%40,%41,%42,%43,%44,%45,%46,%47,%48,%49,%50,%51,%52,%53,%54,%55,%56,%57,%58,%59,%60,%61,%62,%63,"
        "%64,%65,%66,%67,%68,%69,%70,%71,%72,%73,%74,%75,%76,%77,%78,%79,%80,%81,%82,%83,%84,%85,%86,%87,%88,%89,%90,%91,%92,%93,%94,%95,"
        "%96,%97,%98,%99,%100,%101,%102,%103,%104,%105,%106,%107,%108,%109,%110,%111,%112,%113,%114,%115,%116,%117,%118,%119,%120,%121,%122,%123,%124,%125,%126,%127},"
        "da, db, p, 1, 1, 0, %131;}\n"
        : R8(d, 0), R8(d, 8), R8(d, 16), R8(d, 24), R8(d, 32), R8(d, 40), R8(d, 48), R8(d, 56), R8(d, 64), R8(d, 72),
          R8(d, 80), R8(d, 88), R8(d, 96), R8(d, 104), R8(d, 112), R8(d, 120)
        : "r"(da), "r"(db), "r"(scale_d), "n"(TB));
}
__device__ __forceinline__ void wgmma128(float (&d)[64], uint32_t da, uint32_t db) {
    asm volatile(
        "{.reg .b64 da, db; mov.b64 da, {%64, 0x40000040}; mov.b64 db, {%65, 0x40000040};\n"
        "wgmma.mma_async.sync.aligned.m64n128k16.f32.bf16.bf16 "
        "{%0,%1,%2,%3,%4,%5,%6,%7,%8,%9,%10,%11,%12,%13,%14,%15,%16,%17,%18,%19,%20,%21,%22,%23,%24,%25,%26,%27,%28,%29,%30,%31,"
        "%32,%33,%34,%35,%36,%37,%38,%39,%40,%41,%42,%43,%44,%45,%46,%47,%48,%49,%50,%51,%52,%53,%54,%55,%56,%57,%58,%59,%60,%61,%62,%63},"
        "da, db, 1, 1, 1, 0, 1;}\n"
        : R8(d, 0), R8(d, 8), R8(d, 16), R8(d, 24), R8(d, 32), R8(d, 40), R8(d, 48), R8(d, 56)
        : "r"(da), "r"(db));
}
__device__ __forceinline__ void tma_ld(uint32_t dst, const CUtensorMap* m, int c0, int c1, int c2, uint32_t bar) {
    asm volatile("cp.async.bulk.tensor.3d.shared::cluster.global.mbarrier::complete_tx::bytes [%0], [%1,{%2,%3,%4}], [%5];"
                 ::"r"(dst), "l"(m), "r"(c0), "r"(c1), "r"(c2), "r"(bar) : "memory");
}
__device__ __forceinline__ void tma_ld_mc(uint32_t dst, const CUtensorMap* m, int c0, int c1, int c2, uint32_t bar) {
    asm volatile("cp.async.bulk.tensor.3d.shared::cluster.global.mbarrier::complete_tx::bytes.multicast::cluster [%0], [%1,{%2,%3,%4}], [%5], %6;"
                 ::"r"(dst), "l"(m), "r"(c0), "r"(c1), "r"(c2), "r"(bar), "h"((uint16_t)3) : "memory");
}
__device__ __forceinline__ void tma_st(const CUtensorMap* m, int c0, int c1, uint32_t src) {
    asm volatile("cp.async.bulk.tensor.3d.global.shared::cta.bulk_group [%0,{%1,%2,%3}], [%4];"
                 ::"l"(m), "r"(c0), "r"(c1), "r"(0), "r"(src) : "memory");
}
__device__ __forceinline__ void tma_red(const CUtensorMap* m, int c0, int c1, uint32_t src) {
    asm volatile("cp.reduce.async.bulk.tensor.3d.global.shared::cta.add.bulk_group [%0,{%1,%2,%3}], [%4];"
                 ::"l"(m), "r"(c0), "r"(c1), "r"(0), "r"(src) : "memory");
}
__device__ __forceinline__ void bulk_commit() { asm volatile("cp.async.bulk.commit_group;" ::: "memory"); }
template <int N> __device__ __forceinline__ void bulk_wait_read() {
    asm volatile("cp.async.bulk.wait_group.read %0;" ::"n"(N) : "memory");
}
template <int N> __device__ __forceinline__ void bulk_wait() {
    asm volatile("cp.async.bulk.wait_group %0;" ::"n"(N) : "memory");
}
__device__ __forceinline__ void fence_async_smem() { asm volatile("fence.proxy.async.shared::cta;" ::: "memory"); }
__device__ __forceinline__ void fence_async_global() { asm volatile("fence.proxy.async.global;" ::: "memory"); }
__device__ __forceinline__ uint32_t ld_acquire(const uint32_t* p) {
    uint32_t v;
    asm volatile("ld.acquire.gpu.global.u32 %0, [%1];" : "=r"(v) : "l"(p) : "memory");
    return v;
}
__device__ __forceinline__ void red_release(uint32_t* p, uint32_t v) {
    asm volatile("red.release.gpu.global.add.u32 [%0], %1;" ::"l"(p), "r"(v) : "memory");
}
__device__ __forceinline__ void poll_ge(const uint32_t* p, uint32_t target) {
    int it = 0;
    while (ld_acquire(p) < target) {
        __nanosleep(POLL_NS);
        if (++it > SPIN_LIMIT) fail_hard();
    }
}
__device__ __forceinline__ void stsm4(uint32_t addr, uint32_t r0, uint32_t r1, uint32_t r2, uint32_t r3) {
    asm volatile("stmatrix.sync.aligned.m8n8.x4.shared.b16 [%0], {%1,%2,%3,%4};"
                 ::"r"(addr), "r"(r0), "r"(r1), "r"(r2), "r"(r3) : "memory");
}
__device__ __forceinline__ uint32_t pack_bf16(float lo, float hi) {
    uint32_t r;
    asm("cvt.rn.bf16x2.f32 %0, %1, %2;" : "=r"(r) : "f"(hi), "f"(lo));
    return r;
}
__device__ __forceinline__ float bf_lo(uint32_t v) { return __uint_as_float(v << 16); }
__device__ __forceinline__ float bf_hi(uint32_t v) { return __uint_as_float(v & 0xffff0000u); }
__device__ __forceinline__ float rcp_approx(float v) {
    float r;
    asm("rcp.approx.ftz.f32 %0, %1;" : "=f"(r) : "f"(v));
    return r;
}
__device__ __forceinline__ float glu1(float g, float u, float isc) {
    float e, r;
    asm("ex2.approx.ftz.f32 %0, %1;" : "=f"(e) : "f"(g * -1.4426950408889634f));
    asm("rcp.approx.ftz.f32 %0, %1;" : "=f"(r) : "f"(fmaf(e, isc, isc)));
    return u * r;
}
__device__ __forceinline__ uint32_t glu_pair(uint32_t g, uint32_t u, float isc) {
    return pack_bf16(glu1(bf_lo(g), bf_lo(u), isc), glu1(bf_hi(g), bf_hi(u), isc));
}
__device__ __forceinline__ void stsm2(uint32_t addr, uint32_t r0, uint32_t r1) {
    asm volatile("stmatrix.sync.aligned.m8n8.x2.shared.b16 [%0], {%1,%2};" ::"r"(addr), "r"(r0), "r"(r1) : "memory");
}

__global__ void __cluster_dims__(2, 1, 1) __launch_bounds__(384, 1)
fused_kernel(const __grid_constant__ Params P) {
    extern __shared__ uint8_t smem_raw[];
    const uint32_t base = (smem_u32(smem_raw) + 1023) & ~1023u;
    const uint32_t bars = base + OFF_BARS;
    const int warp = __shfl_sync(0xffffffffu, threadIdx.x >> 5, 0), lane = threadIdx.x & 31;
    uint32_t rank;
    asm("mov.u32 %0, %%cluster_ctarank;" : "=r"(rank));
    const int cl = blockIdx.x >> 1;

    if (warp == 0 && elect_one()) {
#pragma unroll
        for (int s = 0; s < NBARS; s++)
            mbar_init(bars + s * 8, s < BAR_EMPTY ? 1 : s < BAR_SFULL ? 16 : s < BAR_SEMPTY ? 4 : 1);
        asm volatile("fence.mbarrier_init.release.cluster;" ::: "memory");
    }
    if (warp == 8 && elect_one()) {
        asm volatile("prefetch.tensormap [%0];" ::"l"(&P.maps[M_WG + rank]) : "memory");
        asm volatile("prefetch.tensormap [%0];" ::"l"(&P.maps[M_XA]) : "memory");
    }
    __syncwarp();
    asm volatile("barrier.cluster.arrive.relaxed.aligned;" ::: "memory");

    if (warp >= 8) {
        asm volatile("setmaxnreg.dec.sync.aligned.u32 40;");
        if (warp == 8) {
            const int slot = gridDim.x >= 128 ? cluster_slot(cl) : cl;
            const int row0 = ((slot & 7) * 2 + rank) * 128, blk0 = (slot >> 3) * 2;
            const bool leader = elect_one();
            asm volatile("barrier.cluster.wait.aligned;" ::: "memory");
            if (leader) {
                const uint32_t t0 = clock();
#pragma unroll 1
                for (int s = 0; s < STAGES; s++) {
                    const uint32_t full = bars + (BAR_FULL + s) * 8, a = base + s * STG_BYTES;
                    while ((uint32_t)clock() - t0 < s * PACE) {}
                    tma_ld_mc(a + A_BYTES + rank * (B_BYTES / 2), &P.maps[M_WG + rank], 0, s * 64, blk0, full);
                    tma_ld(a, &P.maps[M_XA], s * 64, row0, 0, full);
                    mbar_expect_tx(full, STG_BYTES);
                }
            }
            __syncwarp();
        } else {
            asm volatile("barrier.cluster.wait.aligned;" ::: "memory");
        }
        const int it0 = P.off[cl], it1 = P.off[cl + 1];
        asm volatile("barrier.cluster.arrive.relaxed.aligned;" ::: "memory");
        if (warp > 8) {
            uint32_t xph = 0;
            for (int r0 = blockIdx.x * 16; r0 < SEQ; r0 += gridDim.x * 16, xph ^= 1) {
                if (warp == 9 && elect_one()) {
                    if (r0 == blockIdx.x * 16) mbar_wait(bars + (BAR_FULL + STAGES - 1) * 8, 0);
                    mbar_expect_tx(bars + BAR_XROWS * 8, 16 * DM * 2);
                    asm volatile("cp.async.bulk.shared::cluster.global.mbarrier::complete_tx::bytes [%0], [%1], %2, [%3];"
                                 ::"r"(base + OFF_STAGING), "l"(P.x + (size_t)r0 * DM), "r"(16 * DM * 2), "r"(bars + BAR_XROWS * 8) : "memory");
                }
                __syncwarp();
                uint4 w4[4];
#pragma unroll
                for (int q = 0; q < 4; q++) w4[q] = __ldg(reinterpret_cast<const uint4*>(P.gate_w) + q * 32 + lane);
                mbar_wait(bars + BAR_XROWS * 8, xph);
#pragma unroll 1
                for (int r = warp - 9; r < 16; r += 3) {
                    float z0 = 0.f, z1 = 0.f;
#pragma unroll
                    for (int q = 0; q < 4; q++) {
                        uint32_t xa[4];
                        asm volatile("ld.shared.v4.u32 {%0,%1,%2,%3}, [%4];" : "=r"(xa[0]), "=r"(xa[1]), "=r"(xa[2]), "=r"(xa[3])
                                     : "r"(base + OFF_STAGING + r * (DM * 2) + q * 512 + lane * 16) : "memory");
                        const uint32_t* pw = reinterpret_cast<const uint32_t*>(&w4[q]);
#pragma unroll
                        for (int e = 0; e < 4; e++) {
                            uint32_t m;
                            asm("mul.rn.bf16x2 %0, %1, %2;" : "=r"(m) : "r"(xa[e]), "r"(pw[e]));
                            z0 += bf_lo(m);
                            z1 += bf_hi(m);
                        }
                    }
                    float z = z0 + z1;
#pragma unroll
                    for (int o = 16; o > 0; o >>= 1) z += __shfl_xor_sync(0xffffffffu, z, o);
                    if (lane == 0) {
                        z = __bfloat162float(__float2bfloat16(z));
                        const float g = __bfloat162float(__float2bfloat16(__fdividef(1.0f, 1.0f + __expf(-z))));
                        P.gate[r0 + r] = pack_bf16(g, 1.0f - g);
                    }
                }
                fence_async_smem();
                asm volatile("bar.sync 3, 96;" ::: "memory");
                if (warp == 11 && lane == 0) red_release(&P.flags[FLAG_GATE + (r0 >> 7)], 1);
                __syncwarp();
            }
        }
        if (warp == 8) {
            uint32_t sa = base, sbar = bars, ph = 0;
            const bool leader = elect_one();
            for (int it = it0; it < it1; it++) {
                const uint32_t v = P.items[it];
                const int type = it_type(v), col = it_col(v);
                const int rb = it_rp(v) * 2 + rank;
                int k = it_kbeg(v) + (it == it0 ? STAGES : 0);
                const int kend = it_kbeg(v) + it_nks(v);
                const CUtensorMap* mA = &P.maps[type == T_PQ ? (col < 4 ? M_CSRE : M_CSIM) : (type == T_GU ? M_XA : M_HA)];
                uint32_t ready = type == T_OUT ? 0 : ~0u;
                while (k < kend) {
                    const bool km = type == T_OUT && k < 32;
                    const int kseg = km ? min(kend, (k & ~15) + 16) : kend;
                    const CUtensorMap* mB = &P.maps[km ? M_CDRE + (k >> 4) : type == T_OUT ? M_WD : type == T_PQ ? M_XB : M_WG + rank];
                    int b0 = km ? (k & 15) * 64 : 0;
                    int b1 = km ? col * 256 + rank * 128 : (type == T_OUT ? k - 32 : k) * 64;
                    const int b2 = km ? 0 : type == T_GU ? col * 2 : (col & 3) * 4 + rank * 2;
                    const int inc0 = km ? 64 : 0, inc1 = 64 - inc0;
#pragma unroll 1
                    for (; k < kseg; k++) {
                        if (!(ready & 1)) {
                            const int kk = min(k + lane, 87);
                            const uint32_t* f = &P.flags[rb * NTILE1 + (kk < 32 ? (kk >> 2) : 8 + ((kk - 32) >> 1))];
                            int spin = 0;
                            while (true) {
                                ready = __ballot_sync(0xffffffffu, ld_acquire(f) >= 2);
                                if (ready & 1) break;
                                __nanosleep(32);
                                if (++spin > SPIN_LIMIT) fail_hard();
                            }
                            __syncwarp();
                            fence_async_global();
                        }
                        ready >>= 1;
                        mbar_wait(sbar + BAR_EMPTY * 8, ph);
                        if (leader) {
                            mbar_expect_tx(sbar, STG_BYTES);
                            tma_ld(sa, mA, k * 64, rb * 128, 0, sbar);
                            tma_ld_mc(sa + A_BYTES + rank * (B_BYTES / 2), mB, b0, b1, b2, sbar);
                        }
                        __syncwarp();
                        b0 += inc0; b1 += inc1;
                        sa += STG_BYTES; sbar += 8;
                        if (sbar == bars + STAGES * 8) { sa = base; sbar = bars; ph ^= 1; }
                    }
                }
            }
            asm volatile("bar.arrive 2, 128;" ::: "memory");
        } else if (warp < 11) {
            const int w = warp - 9;
            int np1 = 0;
            while (it0 + np1 < it1 && it_type(P.items[it0 + np1]) != T_OUT) np1++;
            auto prep_scales = [&](int j) {
                const uint32_t v = P.items[it0 + j];
                const int rb = it_rp(v) * 2 + rank;
                poll_ge(&P.flags[FLAG_GATE + rb], 8);
                const uint2 gg = __ldcg(reinterpret_cast<const uint2*>(&P.gate[rb * 128 + w * 64 + lane * 2]));
                float s0, s1;
                if (it_type(v) == T_GU) { s0 = fminf(rcp_approx(bf_hi(gg.x)), 1e30f); s1 = fminf(rcp_approx(bf_hi(gg.y)), 1e30f); }
                else if (it_col(v) < 4) { s0 = bf_lo(gg.x); s1 = bf_lo(gg.y); }
                else { s0 = -bf_lo(gg.x); s1 = -bf_lo(gg.y); }
                asm volatile("st.shared.v2.f32 [%0], {%1,%2};" ::"r"(base + OFF_GBUF + (w * 64 + lane * 2) * 4), "f"(s0), "f"(s1) : "memory");
                __syncwarp();
                if (lane == 0) mbar_arrive(bars + (BAR_GREADY + w) * 8);
            };
            int cc = 0;
            for (int j = -1; j < it1 - it0; j++) {
                const uint32_t v = P.items[it0 + max(j, 0)];
                const int type = it_type(v), col = it_col(v);
                const int rb = it_rp(v) * 2 + rank;
                const int nch = j < 0 ? 1 : type == T_GU ? 2 : 4;
                const int c0 = type == T_GU ? 2 * DM + col * 128 : col * 256;
                const bool add = type == T_OUT && !it_first(v);
                uint32_t* flag = &P.flags[type == T_OUT ? FLAG_OUT + (rb * 4 + col) * 2 + w : rb * NTILE1 + (type == T_GU ? 8 + col : col)];
                if (add) {
                    poll_ge(flag, 1);
                    fence_async_global();
                }
                if (j == it1 - it0 - 1) asm volatile("bar.arrive 2, 128;" ::: "memory");
                for (int c = 0; c < nch; c++) {
                    if (j >= 0) {
                        const int buf = cc & 1;
                        mbar_wait(bars + (BAR_SFULL + w * 2 + buf) * 8, (cc >> 1) & 1);
                        if (lane == 0) {
                            const uint32_t src = base + OFF_STAGING + (w * 2 + buf) * CH_BYTES;
                            if (add) tma_red(&P.maps[M_OUT], c0 + c * 64, rb * 128 + w * 64, src);
                            else tma_st(&P.maps[type == T_OUT ? M_OUT : M_HS], c0 + c * 64, rb * 128 + w * 64, src);
                            bulk_commit();
                            if (c > 0) {
                                bulk_wait_read<1>();
                                mbar_arrive(bars + (BAR_SEMPTY + w * 2 + (buf ^ 1)) * 8);
                            }
                        }
                        __syncwarp();
                        cc++;
                    }
                    if (c == 0 && j + 1 < np1) prep_scales(j + 1);
                }
                if (j >= 0) {
                    if (lane == 0) {
                        bulk_wait<0>();
                        mbar_arrive(bars + (BAR_SEMPTY + w * 2 + ((cc - 1) & 1)) * 8);
                        if (!add) {
                            fence_async_global();
                            red_release(flag, 1);
                        }
                    }
                    __syncwarp();
                }
            }
        } else {
            asm volatile("bar.sync 2, 128;" ::: "memory");
            uint32_t old = 0;
            if (lane == 0)
                asm volatile("atom.acq_rel.gpu.global.inc.u32 %0, [%1], %2;" : "=r"(old) : "l"(&P.flags[NFLAGS]), "r"(gridDim.x - 1) : "memory");
            old = __shfl_sync(0xffffffffu, old, 0);
            if (old == gridDim.x - 1)
                for (int i = lane; i < NFLAGS; i += 32) P.flags[i] = 0;
        }
        asm volatile("barrier.cluster.wait.aligned;" ::: "memory");
    } else {
        asm volatile("setmaxnreg.inc.sync.aligned.u32 232;");
        const int it0 = P.off[cl], it1 = P.off[cl + 1];
        const int wg = warp >> 2;
        float acc[128];
        uint32_t pk[64];
#pragma unroll
        for (int i = 0; i < 64; i++) asm volatile("" : "=r"(pk[i]));
        int ptype = -1;
        int cc = 0;
        float isc0 = 0.f, isc1 = 0.f;
        const uint32_t stg_row = base + OFF_STAGING + wg * 2 * CH_BYTES + ((warp & 3) * 16 + (lane & 15)) * 128;
        const uint32_t stg2 = stg_row + ((lane & 7) << 4);
        const uint32_t stg4 = stg_row + (((lane >> 4) ^ (lane & 7)) << 4);
        const uint32_t empty_remote = mapa(bars + BAR_EMPTY * 8, lane & 1);
        const uint32_t da0 = uniform(desc_lo(base + wg * (A_BYTES / 2), 16));
        const uint32_t db0 = uniform(desc_lo(base + A_BYTES, 16));
        const uint32_t sbar = bars + wg * 16;
        const bool rel = lane < 2;
        uint32_t ph = 0, gph = 0;

        auto step = [&](auto Jc, bool km, bool fresh, bool endgrp, auto side) {
            constexpr int J = decltype(Jc)::value;
            const uint32_t da = da0 + J * (STG_BYTES >> 4), db = db0 + J * (STG_BYTES >> 4);
            const bool hold = J == STAGES - 2 && endgrp && wg == 1;
            if (hold) {
                wg_wait<0>();
                if (rel) mbar_arrive_cluster(empty_remote + ((J + STAGES - 1) % STAGES) * 8);
                asm volatile("bar.sync 1, 256;" ::: "memory");
            }
            if (km) {
                wg_fence();
                wgmma256<0>(acc, da, db, !fresh);
                wgmma256<0>(acc, da + 2, db + 2, 1);
                wgmma256<0>(acc, da + 4, db + 4, 1);
                wgmma256<0>(acc, da + 6, db + 6, 1);
                wg_commit();
            } else {
                constexpr uint32_t NM = (512 - 1) << 16;
                wg_fence();
                wgmma256<1>(acc, da, db + NM, !fresh);
                wgmma256<1>(acc, da + 2, db + NM + 128, 1);
                wgmma256<1>(acc, da + 4, db + NM + 256, 1);
                wgmma256<1>(acc, da + 6, db + NM + 384, 1);
                wg_commit();
            }
            if (J == STAGES - 1 && endgrp && wg == 0) asm volatile("bar.arrive 1, 256;" ::: "memory");
            if (J == STAGES - 1) ph ^= 1;
            const uint32_t nbar = bars + (BAR_FULL + (J + 1) % STAGES) * 8;
            const bool ok = mbar_test(nbar, ph);
            wg_wait<1>();
            if (rel && !fresh && !hold) mbar_arrive_cluster(empty_remote + ((J + STAGES - 1) % STAGES) * 8);
            side();
            if (!ok) mbar_wait_c(nbar, ph);
        };
        auto chunk_begin = [&]() { mbar_wait_c(sbar + (BAR_SEMPTY + (cc & 1)) * 8, ((cc >> 1) & 1) ^ 1); };
        auto chunk_end = [&]() {
            fence_async_smem();
            __syncwarp();
            if (lane == 0) mbar_arrive(sbar + (BAR_SFULL + (cc & 1)) * 8);
            cc++;
        };

        uint32_t v = P.items[it0];
        int type = it_type(v), ngrp = it_nks(v) >> 2, nkm = 0;
        asm volatile("barrier.cluster.wait.aligned;" ::: "memory");
        mbar_wait_c(bars + BAR_FULL * 8, 0);
        for (int left = it1 - it0 - 1;; left--) {
            const int npend = ptype == T_GU ? 4 : ptype >= 0 ? 2 : 0;
#pragma unroll 1
            for (int g = 0; g < ngrp - (left == 0); g++) {
                const bool km = g < nkm, pend = g < npend;
                static_for<STAGES>([&](auto Jc) {
                    constexpr int J = decltype(Jc)::value;
                    step(Jc, km, J == 0 && g == 0, g == ngrp - 1, [&]() {
                        if (!pend) return;
                        const uint32_t boff = (cc & 1) * CH_BYTES;
                        if (ptype == T_GU) {
                            if (J == 0 && g == 2) chunk_begin();
                            uint32_t t[4];
#pragma unroll
                            for (int q = 0; q < 4; q++) {
                                constexpr int o = J * 2;
                                const int b = (q >> 1) * 32 + (q & 1);
                                const uint32_t lo = g & 1 ? pk[b + 8 + o] : pk[b + o];
                                const uint32_t hi = g & 1 ? pk[b + 24 + o] : pk[b + 16 + o];
                                t[q] = g & 2 ? hi : lo;
                            }
                            stsm2((stg2 + boff) ^ (((g & 1) << 6) | (J << 4)), glu_pair(t[0], t[2], isc0), glu_pair(t[1], t[3], isc1));
                        } else {
                            if (!(J & 1) && (J || g)) chunk_begin();
                            const uint32_t dst = (stg4 + boff) ^ ((J & 1) << 6);
                            if (g == 0) {
                                stsm4(dst, pk[J * 8], pk[J * 8 + 1], pk[J * 8 + 2], pk[J * 8 + 3]);
                                stsm4(dst ^ 32, pk[J * 8 + 4], pk[J * 8 + 5], pk[J * 8 + 6], pk[J * 8 + 7]);
                            } else {
                                stsm4(dst, pk[32 + J * 8], pk[32 + J * 8 + 1], pk[32 + J * 8 + 2], pk[32 + J * 8 + 3]);
                                stsm4(dst ^ 32, pk[32 + J * 8 + 4], pk[32 + J * 8 + 5], pk[32 + J * 8 + 6], pk[32 + J * 8 + 7]);
                            }
                        }
                        if ((J & 1) && (ptype != T_GU || (J == STAGES - 1 && (g & 1)))) chunk_end();
                    });
                });
            }
            if (left == 0) break;
            float sc0 = 1.f, sc1 = 1.f;
            if (type != T_OUT) {
                mbar_wait_c(bars + (BAR_GREADY + wg) * 8, gph);
                gph ^= 1;
                const uint32_t ga = base + OFF_GBUF + (wg * 64 + (warp & 3) * 16 + (lane >> 2)) * 4;
                asm volatile("ld.shared.f32 %0, [%1];" : "=f"(sc0) : "r"(ga) : "memory");
                asm volatile("ld.shared.f32 %0, [%1+32];" : "=f"(sc1) : "r"(ga) : "memory");
            }
            chunk_begin();
            ptype = type;
            v = P.items[it1 - left];
            type = it_type(v);
            ngrp = uniform(it_nks(v) >> 2);
            nkm = uniform(type == T_OUT ? 8 - (it_kbeg(v) >> 2) : 0);
            wg_wait<0>();
#pragma unroll
            for (int i = 0; i < 128; i++) asm volatile("" : "+f"(acc[i])::"memory");
            if (rel) mbar_arrive_cluster(empty_remote + (STAGES - 1) * 8);
            if (ptype == T_PQ) {
#pragma unroll
                for (int i = 0; i < 128; i++) acc[i] *= i & 2 ? sc1 : sc0;
            }
#pragma unroll
            for (int m = 0; m < 64; m++) pk[m] = pack_bf16(acc[m * 2], acc[m * 2 + 1]);
            isc0 = sc0; isc1 = sc1;
        }
        float hacc[2][64];
        auto half = [&](auto Hc, auto Jc) {
            constexpr int H = decltype(Hc)::value, J = decltype(Jc)::value;
            const uint32_t da = da0 + J * (STG_BYTES >> 4);
            const uint32_t db = db0 + J * (STG_BYTES >> 4) + ((512 - 1) << 16) + H * (B_BYTES >> 5);
            if (H == 0 && J) mbar_wait_c(bars + (BAR_FULL + J) * 8, ph);
            wg_fence();
            wgmma128(hacc[H], da, db);
            wgmma128(hacc[H], da + 2, db + 128);
            wgmma128(hacc[H], da + 4, db + 256);
            wgmma128(hacc[H], da + 6, db + 384);
            wg_commit();
        };
        auto store_half = [&](auto Hc) {
            constexpr int H = decltype(Hc)::value;
#pragma unroll
            for (int i = 0; i < 64; i++) asm volatile("" : "+f"(hacc[H][i])::"memory");
#pragma unroll
            for (int c = 0; c < 2; c++) {
                const uint32_t boff = (cc & 1) * CH_BYTES;
                chunk_begin();
#pragma unroll
                for (int j = 0; j < 4; j++) {
                    const float* a = &hacc[H][c * 32 + j * 8];
                    stsm4((stg4 + boff) ^ (j << 5), pack_bf16(a[0], a[1]), pack_bf16(a[2], a[3]), pack_bf16(a[4], a[5]), pack_bf16(a[6], a[7]));
                }
                chunk_end();
            }
        };
        wg_wait<0>();
#pragma unroll
        for (int i = 0; i < 128; i++) asm volatile("" : "+f"(acc[i])::"memory");
        if (rel) mbar_arrive_cluster(empty_remote + (STAGES - 1) * 8);
#pragma unroll
        for (int i = 0; i < 128; i++) asm volatile("mov.b32 %0, %1;" : "=f"(hacc[i / 64][i % 64]) : "f"(acc[i]));
        if (wg == 1) asm volatile("bar.sync 1, 256;" ::: "memory");
        half(IC<0>{}, IC<0>{});
        half(IC<0>{}, IC<1>{});
        half(IC<0>{}, IC<2>{});
        half(IC<1>{}, IC<0>{});
        half(IC<1>{}, IC<1>{});
        half(IC<0>{}, IC<3>{});
        asm volatile("barrier.cluster.arrive.relaxed.aligned;" ::: "memory");
        half(IC<1>{}, IC<2>{});
        half(IC<1>{}, IC<3>{});
        if (wg == 0) asm volatile("bar.arrive 1, 256;" ::: "memory");
        wg_wait<2>();
        store_half(IC<0>{});
        wg_wait<0>();
        store_half(IC<1>{});
        asm volatile("barrier.cluster.wait.aligned;" ::: "memory");
    }
}

typedef CUresult (*EncFn)(CUtensorMap*, CUtensorMapDataType, cuuint32_t, void*, const cuuint64_t*, const cuuint64_t*,
                          const cuuint32_t*, const cuuint32_t*, CUtensorMapInterleave, CUtensorMapSwizzle,
                          CUtensorMapL2promotion, CUtensorMapFloatOOBfill);

void enc3(EncFn f, CUtensorMap* m, const void* p, uint64_t d0, uint64_t d1, uint64_t d2, uint64_t s1, uint64_t s2,
          uint32_t b0, uint32_t b1, uint32_t b2) {
    cuuint64_t gd[3] = {d0, d1, d2};
    cuuint64_t gs[2] = {s1, s2};
    cuuint32_t bd[3] = {b0, b1, b2};
    cuuint32_t es[3] = {1, 1, 1};
    f(m, CU_TENSOR_MAP_DATA_TYPE_BFLOAT16, 3, const_cast<void*>(p), gd, gs, bd, es, CU_TENSOR_MAP_INTERLEAVE_NONE,
      CU_TENSOR_MAP_SWIZZLE_128B, CU_TENSOR_MAP_L2_PROMOTION_L2_128B, CU_TENSOR_MAP_FLOAT_OOB_FILL_NONE);
}
void enc_rowmajor(EncFn f, CUtensorMap* m, const void* p, int rows, int cols, int brows) {
    enc3(f, m, p, cols, rows, 1, (uint64_t)cols * 2, (uint64_t)cols * 2 * rows, 64, brows, 1);
}
void enc_nmajor(EncFn f, CUtensorMap* m, const void* p, int krows, int cols) {
    enc3(f, m, p, 64, krows, cols / 64, (uint64_t)cols * 2, 128, 64, 64, 2);
}

int build_schedule(Params& P, int max_clusters) {
    int n = 0, ncl;
    if (max_clusters >= 66) {
        ncl = 66;
        for (int c = 0; c < 64; c++) {
            const int slot = cluster_slot(c), r = slot & 7, j = slot >> 3;
            const int q = j >> 1, X = (j & 1) * 2, Y = X + 1;
            const bool b = r >= 4 && (j & 1);
            const bool b2 = b && r >= 6;
            P.off[c] = n;
            P.items[n++] = mk_item(T_GU, r, j, 0, 16);
            P.items[n++] = mk_item(T_PQ, r, j, 0, 32);
            P.items[n++] = mk_item(T_GU, r, slot < 2 ? 27 : 8 + j, 0, 16);
            P.items[n++] = mk_item(T_GU, r, 16 + j, 0, 16);
            if (q == 0 && !b) P.items[n++] = mk_item(T_OUT, r, X, 40, 48);
            if (q == 0 && b) { P.items[n++] = mk_item(T_GU, r, 26, 0, 16); P.items[n++] = mk_item(T_OUT, r, X, 56, 32); }
            if (q == 1 && !b2) P.items[n++] = mk_item(T_OUT, r, Y, 40, 48);
            if (q == 1 && b2) { P.items[n++] = mk_item(T_OUT, r, Y, 0, 24, 1); P.items[n++] = mk_item(T_OUT, r, Y, 64, 24); }
            if (q == 2) { P.items[n++] = mk_item(T_OUT, r, X, 0, 24, 1); P.items[n++] = mk_item(T_OUT, r, Y, b2 ? 24 : 16, 24); }
            if (q == 3) P.items[n++] = mk_item(T_GU, r, 24 + (j & 1), 0, 16);
            if (q == 3 && !b) { P.items[n++] = mk_item(T_OUT, r, Y, 0, 16, 1); P.items[n++] = mk_item(T_OUT, r, X, 24, 16); }
            if (q == 3 && b) P.items[n++] = mk_item(T_OUT, r, X, 24, 32);
        }
        for (int e = 0; e < 2; e++) {
            P.off[64 + e] = n;
            for (int t = 0; t < 4; t++) P.items[n++] = mk_item(T_GU, e + 2 * t, t ? 27 : 8, 0, 16);
            for (int t = 0; t < 2; t++) P.items[n++] = mk_item(T_GU, e + 2 * t, 26, 0, 16);
            P.items[n++] = mk_item(T_OUT, e + 4, 3, 0, 16, 1);
            P.items[n++] = mk_item(T_OUT, e + 6, 3, 48, 16);
        }
    } else if (max_clusters >= 64) {
        ncl = 64;
        for (int c = 0; c < ncl; c++) {
            const int r = cluster_slot(c) & 7, j = cluster_slot(c) >> 3;
            P.off[c] = n;
            for (int q = 0; q < (j < 4 ? 4 : 3); q++) {
                if (q == 1) P.items[n++] = mk_item(T_PQ, r, j, 0, 32);
                P.items[n++] = mk_item(T_GU, r, q * 8 + j, 0, 16);
            }
            P.items[n++] = j < 4 ? mk_item(T_OUT, r, j, 48, 40) : mk_item(T_OUT, r, j - 4, 0, 48, 1);
        }
    } else {
        ncl = max_clusters < 1 ? 1 : max_clusters;
        for (int c = 0; c < ncl; c++) {
            P.off[c] = n;
            for (int t = c; t < 8 * NTILE1; t += ncl) {
                const int r = t & 7, j = t >> 3;
                P.items[n++] = j >= 8 && j < 16 ? mk_item(T_PQ, r, j - 8, 0, 32) : mk_item(T_GU, r, j < 8 ? j : j - 8, 0, 16);
            }
            for (int t = c; t < 64; t += ncl) P.items[n++] = mk_item(T_OUT, t & 7, (t >> 3) & 3, (t >> 5) * 44, 44, t < 32);
        }
    }
    P.off[ncl] = n;
    return ncl;
}

}

extern "C" void kernel_launch(void* const* d_in, const int* in_sizes, int n_in, void* d_out, int out_size) {
    static Params P;
    static int ncl = 0;
    static const void* key[11];
    bool same = ncl > 0;
    for (int i = 0; i < 10; i++) same = same && key[i] == d_in[i];
    same = same && key[10] == d_out;
    if (!same) {
        for (int i = 0; i < 10; i++) key[i] = d_in[i];
        key[10] = d_out;
        EncFn f = nullptr;
        cudaDriverEntryPointQueryResult q;
        cudaGetDriverEntryPoint("cuTensorMapEncodeTiled", (void**)&f, cudaEnableDefault, &q);
        void* H = nullptr;
        cudaGetSymbolAddress(&H, g_H);
        enc_rowmajor(f, &P.maps[M_CSRE], d_in[1], SEQ, SEQ, 128);
        enc_rowmajor(f, &P.maps[M_CSIM], d_in[2], SEQ, SEQ, 128);
        enc_rowmajor(f, &P.maps[M_XA], d_in[0], SEQ, DM, 128);
        enc_nmajor(f, &P.maps[M_XB], d_in[0], SEQ, DM);
        enc_nmajor(f, &P.maps[M_WG], d_in[6], DM, FF);
        enc_nmajor(f, &P.maps[M_WU], d_in[7], DM, FF);
        enc_rowmajor(f, &P.maps[M_HA], H, SEQ, KH, 128);
        enc_rowmajor(f, &P.maps[M_HS], H, SEQ, KH, 64);
        enc_rowmajor(f, &P.maps[M_CDRE], d_in[3], DM, DM, 128);
        enc_rowmajor(f, &P.maps[M_CDIM], d_in[4], DM, DM, 128);
        enc_nmajor(f, &P.maps[M_WD], d_in[8], FF, DM);
        enc_rowmajor(f, &P.maps[M_OUT], d_out, SEQ, DM, 64);
        P.x = (const __nv_bfloat16*)d_in[0];
        P.gate_w = (const __nv_bfloat16*)d_in[9];
        cudaGetSymbolAddress((void**)&P.gate, g_gate);
        cudaGetSymbolAddress((void**)&P.flags, g_flags);
        cudaFuncSetAttribute(fused_kernel, cudaFuncAttributeMaxDynamicSharedMemorySize, SMEM_BYTES);
        cudaLaunchConfig_t cfg = {};
        cfg.gridDim = dim3(2 * MAX_CLUSTERS);
        cfg.blockDim = dim3(384);
        cfg.dynamicSmemBytes = SMEM_BYTES;
        cudaLaunchAttribute at[1];
        at[0].id = cudaLaunchAttributeClusterDimension;
        at[0].val.clusterDim.x = 2; at[0].val.clusterDim.y = 1; at[0].val.clusterDim.z = 1;
        cfg.attrs = at;
        cfg.numAttrs = 1;
        int maxc = 0;
        cudaOccupancyMaxActiveClusters(&maxc, fused_kernel, &cfg);
        ncl = build_schedule(P, maxc > MAX_CLUSTERS ? MAX_CLUSTERS : maxc);
    }
    fused_kernel<<<2 * ncl, 384, SMEM_BYTES>>>(P);
}
```
